```python
import torch

def _softmax(x, axis=-1):
    return torch.softmax(x, dim=axis)
def _gelu(x):
    return torch.nn.functional.gelu(x, approximate="tanh")
def _silu(x):
    return torch.nn.functional.silu(x)
def _sigmoid(x):
    return torch.sigmoid(x)
def _layernorm(x, axis=-1, eps=1e-5):
    m = x.mean(dim=axis, keepdim=True)
    v = x.var(dim=axis, keepdim=True, unbiased=False)
    return (x - m) / torch.sqrt(v + eps)
def _scatter_add(tgt, idx, src, axis=0):
    return tgt.clone().index_add_(axis, idx, src)
def _segment_sum(src, seg, n):
    out = torch.zeros((n,) + src.shape[1:], dtype=src.dtype)
    return out.index_add_(0, seg, src)
def _pad(x, pw):
    flat = tuple(v for pair in reversed(pw) for v in pair)
    return torch.nn.functional.pad(x, flat)

kernel_name = 'standalone__channel_attn_cbam__vision'

def setup_inputs():

    _w = (lambda a: (lambda t: t.to(torch.bfloat16) if t.is_floating_point() else t)(torch.as_tensor(a)))
    H = W = 256
    C = 384
    r = max(C // 4, 1)
    return {
        "x": _w((lambda *s: torch.randn(*s, dtype=torch.bfloat16) * 0.1)(1, H, W, C) + (lambda *s: torch.randn(*s, dtype=torch.bfloat16) * 0.1)(1, 1, 1, C) * 2.0),
        "w1": _w((lambda *s: torch.randn(*s, dtype=torch.bfloat16) * 0.1)(C, r)),
        "w2": _w((lambda *s: torch.randn(*s, dtype=torch.bfloat16) * 0.1)(r, C)),
    }

def reference(x, w1, w2):
    B, H, W, C = x.shape
    xf = x.reshape(B, H * W, C)
    gap = torch.mean(xf, 1)
    gmp = torch.amax(xf, 1)
    h_a = gap @ w1
    h_a = h_a * (lambda x, dt: x.to(dt))(h_a > 0, h_a.dtype)
    h_m = gmp @ w1
    h_m = h_m * (lambda x, dt: x.to(dt))(h_m > 0, h_m.dtype)
    scale = _sigmoid(h_a @ w2 + h_m @ w2)
    return x * scale[:, None, None, :]
```

```cpp
#include <cuda_runtime.h>
#include <cuda_bf16.h>
#include <stdint.h>

namespace cbam {

constexpr int C = 384;
constexpr int HID = 96;
constexpr int NT = 384;
constexpr int ROWS = 65536;
constexpr int ROW_BYTES = C * 2;
constexpr int NS = 6;
constexpr int PROWS = 48;
constexpr int PASS_BYTES = NT * 16;
#define CBAM_SMP 36
#define CBAM_RGP 27
#define CBAM_RGL 18
#define CBAM_W 8
constexpr int SMP = CBAM_SMP;
constexpr int RGP = CBAM_RGP;
constexpr int RGL = CBAM_RGL;
constexpr int NPN = SMP + RGP;
constexpr int NPL = SMP + RGL;
constexpr int WIN = CBAM_W;
constexpr int MAXNG = 22;
constexpr int NL1 = 12;
constexpr int L1G = NL1 / NS;
constexpr int NREP = 4;
constexpr unsigned SPIN_LIMIT = 1u << 22;

struct __align__(128) Scratch {
    uint4 part[NS][MAXNG][32];
    unsigned long long hid[NREP][128];
    unsigned epoch;
};
__device__ Scratch g_s;

#define TS(i)

constexpr int SM_DATA = SMP * PASS_BYTES;
constexpr int SM_RED = SM_DATA;
constexpr int SM_MISC = SM_RED + 6144;
constexpr int SM_TOTAL = SM_MISC + 1024;

__device__ __forceinline__ uint4 ldg_stream(const void* p, unsigned long long pol) {
    uint4 v;
    asm volatile("ld.global.nc.L1::no_allocate.L2::cache_hint.v4.u32 {%0,%1,%2,%3}, [%4], %5;"
                 : "=r"(v.x), "=r"(v.y), "=r"(v.z), "=r"(v.w) : "l"(p), "l"(pol));
    return v;
}
__device__ __forceinline__ uint4 ldg16(const void* p) {
    uint4 v;
    asm volatile("ld.global.nc.v4.u32 {%0,%1,%2,%3}, [%4];" : "=r"(v.x), "=r"(v.y), "=r"(v.z), "=r"(v.w) : "l"(p));
    return v;
}
__device__ __forceinline__ uint2 ldg8(const void* p) {
    uint2 v;
    asm volatile("ld.global.nc.v2.u32 {%0,%1}, [%2];" : "=r"(v.x), "=r"(v.y) : "l"(p));
    return v;
}
__device__ __forceinline__ void stg16(void* p, uint4 v) {
    asm volatile("st.global.v4.u32 [%0], {%1,%2,%3,%4};" :: "l"(p), "r"(v.x), "r"(v.y), "r"(v.z), "r"(v.w) : "memory");
}
__device__ __forceinline__ uint4 lds16(unsigned a) {
    uint4 v;
    asm volatile("ld.shared.v4.u32 {%0,%1,%2,%3}, [%4];" : "=r"(v.x), "=r"(v.y), "=r"(v.z), "=r"(v.w) : "r"(a) : "memory");
    return v;
}
__device__ __forceinline__ void sts16(unsigned a, uint4 v) {
    asm volatile("st.shared.v4.u32 [%0], {%1,%2,%3,%4};" :: "r"(a), "r"(v.x), "r"(v.y), "r"(v.z), "r"(v.w) : "memory");
}
__device__ __forceinline__ uint4 ld_poll16(const void* p) {
    unsigned long long a, b;
    asm volatile("ld.relaxed.gpu.global.v2.u64 {%0,%1}, [%2];" : "=l"(a), "=l"(b) : "l"(p) : "memory");
    return make_uint4((unsigned)a, (unsigned)(a >> 32), (unsigned)b, (unsigned)(b >> 32));
}
__device__ __forceinline__ void ld_poll16_if(uint4& v, const void* p, unsigned pred) {
    asm volatile("{ .reg .pred p; .reg .b64 a, b; setp.ne.u32 p, %5, 0;\n\t"
                 "@p ld.relaxed.gpu.global.v2.b64 {a, b}, [%4];\n\t"
                 "@p mov.b64 {%0,%1}, a;\n\t@p mov.b64 {%2,%3}, b; }"
                 : "+r"(v.x), "+r"(v.y), "+r"(v.z), "+r"(v.w) : "l"(p), "r"(pred) : "memory");
}
__device__ __forceinline__ void st_pkt8(void* p, unsigned lo, unsigned hi) {
    unsigned long long r = (unsigned long long)lo | ((unsigned long long)hi << 32);
    asm volatile("st.relaxed.gpu.global.u64 [%0], %1;" :: "l"(p), "l"(r) : "memory");
}
__device__ __forceinline__ void st_pkt16(void* p, unsigned a, unsigned b, unsigned c, unsigned d) {
    unsigned long long r0 = (unsigned long long)a | ((unsigned long long)b << 32);
    unsigned long long r1 = (unsigned long long)c | ((unsigned long long)d << 32);
    asm volatile("st.relaxed.gpu.global.v2.u64 [%0], {%1,%2};" :: "l"(p), "l"(r0), "l"(r1) : "memory");
}
__device__ __forceinline__ unsigned bmax2(unsigned a, unsigned b) {
    unsigned r;
    asm("max.NaN.bf16x2 %0, %1, %2;" : "=r"(r) : "r"(a), "r"(b));
    return r;
}
__device__ __forceinline__ unsigned bmul2(unsigned a, unsigned b) {
    unsigned r;
    asm("mul.rn.bf16x2 %0, %1, %2;" : "=r"(r) : "r"(a), "r"(b));
    return r;
}
__device__ __forceinline__ float bf_lo(unsigned u) { return __uint_as_float(u << 16); }
__device__ __forceinline__ float bf_hi(unsigned u) { return __uint_as_float(u & 0xffff0000u); }
__device__ __forceinline__ unsigned f2bf(float f) { return (unsigned)__bfloat16_as_ushort(__float2bfloat16_rn(f)); }
__device__ __forceinline__ float rbf(float f) { return __bfloat162float(__float2bfloat16_rn(f)); }

__device__ __forceinline__ void accum(const uint4& v, float (&s)[8], unsigned (&m)[4]) {
    s[0] += bf_lo(v.x); s[1] += bf_hi(v.x);
    s[2] += bf_lo(v.y); s[3] += bf_hi(v.y);
    s[4] += bf_lo(v.z); s[5] += bf_hi(v.z);
    s[6] += bf_lo(v.w); s[7] += bf_hi(v.w);
    m[0] = bmax2(m[0], v.x); m[1] = bmax2(m[1], v.y);
    m[2] = bmax2(m[2], v.z); m[3] = bmax2(m[3], v.w);
}
__device__ __forceinline__ uint4 scale4(const uint4& v, const uint4& sc) {
    return make_uint4(bmul2(v.x, sc.x), bmul2(v.y, sc.y), bmul2(v.z, sc.z), bmul2(v.w, sc.w));
}
template <int MASK>
__device__ __forceinline__ float rs_step(float lo, float hi, int lane) {
    const bool up = lane & MASK;
    const float keep = up ? hi : lo, send = up ? lo : hi;
    return keep + __shfl_xor_sync(~0u, send, MASK);
}
template <int MASK>
__device__ __forceinline__ unsigned rs_step_max(unsigned lo, unsigned hi, int lane) {
    const bool up = lane & MASK;
    const unsigned keep = up ? hi : lo, send = up ? lo : hi;
    return bmax2(keep, __shfl_xor_sync(~0u, send, MASK));
}

template <bool L1>
__device__ __forceinline__ void body(const char* __restrict__ x, const char* __restrict__ w1,
                                     const char* __restrict__ w2, char* __restrict__ out, char* smem) {
    constexpr int NP = L1 ? NPL : NPN;
    const unsigned sbase = (unsigned)__cvta_generic_to_shared(smem);
    const int t = threadIdx.x, lane = t & 31, warp = t >> 5;
    const int b = blockIdx.x, ng = gridDim.x / NS;
    const int slice = b % NS, grp = b / NS;
    TS(0);

    unsigned long long pol_first;
    asm volatile("createpolicy.fractional.L2::evict_first.b64 %0, 1.0;" : "=l"(pol_first));

    const unsigned col = slice * 128 + (t & 7) * 16;
    const unsigned off0 = (unsigned)(grp * PROWS + (t >> 3)) * ROW_BYTES + col;
    const unsigned pstride = (unsigned)ng * PROWS * ROW_BYTES;
    const unsigned off1 = off0 + NPL * pstride - L1G * PROWS * ROW_BYTES;
    const unsigned pstride1 = pstride - L1G * PROWS * ROW_BYTES;
    auto goff = [&](int i) -> unsigned { return i < NPL ? off0 + i * pstride : off1 + (i - NPL) * pstride1; };
    const bool last_ok = L1 || goff(NP - 1) < (unsigned)ROWS * ROW_BYTES;
    const unsigned sm_t = sbase + t * 16;

    float s[8];
    unsigned m[4];
#pragma unroll
    for (int i = 0; i < 8; i++) s[i] = 0.f;
#pragma unroll
    for (int i = 0; i < 4; i++) m[i] = 0xff80ff80u;

    const int cap_rows = (ng * NPL + (ng - L1G) * (NPN - NPL)) * PROWS;
    const int ovf_units = cap_rows < ROWS ? (ROWS - cap_rows) >> 2 : 0;
    const unsigned ovf_base = (unsigned)(cap_rows + (lane >> 3)) * ROW_BYTES + col;
    for (int u = warp * ng + grp; u < ovf_units; u += 12 * ng)
        accum(ldg16(x + ovf_base + (size_t)u * 4 * ROW_BYTES), s, m);

    uint4 d[NP];
    unsigned epoch;
#pragma unroll
    for (int i = 0; i < NP + WIN; i++) {
        if (i < NP - 1) d[i] = ldg_stream(x + goff(i), pol_first);
        if (i == NP - 1) { d[i] = make_uint4(0, 0, 0, 0); if (last_ok) d[i] = ldg_stream(x + goff(i), pol_first); }
        if (i == WIN - 1)
            asm volatile("ld.relaxed.gpu.global.u32 %0, [%1];" : "=r"(epoch) : "l"(&g_s.epoch) : "memory");
        if (i >= WIN) {
            const int j = i - WIN;
            if (j < NP - 1 || last_ok) accum(d[j], s, m);
            if (j < SMP) sts16(sm_t + j * PASS_BYTES, d[j]);
        }
    }
    TS(1);
    const unsigned tag32 = epoch + 1u;
    const unsigned tag16 = (epoch % 65535u) + 1u;

    {
        const float a0 = rs_step<16>(s[0], s[4], lane), a1 = rs_step<16>(s[1], s[5], lane);
        const float a2 = rs_step<16>(s[2], s[6], lane), a3 = rs_step<16>(s[3], s[7], lane);
        const unsigned k0 = rs_step_max<16>(m[0], m[2], lane), k1 = rs_step_max<16>(m[1], m[3], lane);
        const float c0 = rs_step<8>(a0, a2, lane), c1 = rs_step<8>(a1, a3, lane);
        const unsigned km = rs_step_max<8>(k0, k1, lane);
        const int cp = (lane & 7) * 4 + (lane >> 4) * 2 + ((lane >> 3) & 1);
        sts16(sbase + SM_RED + (warp * 32 + cp) * 16, make_uint4(__float_as_uint(c0), __float_as_uint(c1), km, 0));
        __syncthreads();
        if (warp < 4) {
            const int cpp = warp * 8 + (lane & 7), sw = (lane >> 3) * 3;
            const uint4 e0 = lds16(sbase + SM_RED + ((sw + 0) * 32 + cpp) * 16);
            const uint4 e1 = lds16(sbase + SM_RED + ((sw + 1) * 32 + cpp) * 16);
            const uint4 e2 = lds16(sbase + SM_RED + ((sw + 2) * 32 + cpp) * 16);
            float u0 = (__uint_as_float(e0.x) + __uint_as_float(e1.x)) + __uint_as_float(e2.x);
            float u1 = (__uint_as_float(e0.y) + __uint_as_float(e1.y)) + __uint_as_float(e2.y);
            unsigned um = bmax2(bmax2(e0.z, e1.z), e2.z);
            u0 += __shfl_xor_sync(~0u, u0, 8); u1 += __shfl_xor_sync(~0u, u1, 8); um = bmax2(um, __shfl_xor_sync(~0u, um, 8));
            u0 += __shfl_xor_sync(~0u, u0, 16); u1 += __shfl_xor_sync(~0u, u1, 16); um = bmax2(um, __shfl_xor_sync(~0u, um, 16));
            if (lane < 8)
                st_pkt16(&g_s.part[slice][grp][cpp], __float_as_uint(u0), (um & 0xffffu) | (tag16 << 16),
                         __float_as_uint(u1), (um >> 16) | (tag16 << 16));
        }
    }
    TS(2);
    const uint4 w2a = ldg16(w2 + (size_t)((t >> 3) * 2) * ROW_BYTES + slice * 128 + (t & 7) * 16);
    const uint4 w2b = ldg16(w2 + (size_t)((t >> 3) * 2 + 1) * ROW_BYTES + slice * 128 + (t & 7) * 16);

    float* misc = reinterpret_cast<float*>(smem + SM_MISC);
    if constexpr (L1) {
        const int cp = t >> 1, half = t & 1;
        const uint2 w1a = ldg8(w1 + ((size_t)(2 * cp) * HID + 8 * b + 4 * half) * 2);
        const uint2 w1b = ldg8(w1 + ((size_t)(2 * cp + 1) * HID + 8 * b + 4 * half) * 2);
        constexpr int HG = MAXNG / 2;
        uint4 q[HG];
        const uint4* src = &g_s.part[cp >> 5][half * HG][cp & 31];
        unsigned pending = 0;
#pragma unroll
        for (int g = 0; g < HG; g++) {
            q[g] = make_uint4(0u, 0xff80u, 0u, 0xff80u);
            if (half * HG + g < ng) pending |= 1u << g;
        }
        unsigned spins = 0;
        while (pending) {
#pragma unroll
            for (int g = 0; g < HG; g++) ld_poll16_if(q[g], src + g * 32, pending & (1u << g));
#pragma unroll
            for (int g = 0; g < HG; g++)
                if ((q[g].y >> 16) == tag16 && (q[g].w >> 16) == tag16) pending &= ~(1u << g);
            if (++spins > SPIN_LIMIT) __trap();
        }
        float t0 = 0.f, t1 = 0.f;
        unsigned mx = 0xff80ff80u;
#pragma unroll
        for (int g = 0; g < HG; g++) {
            t0 += __uint_as_float(q[g].x); t1 += __uint_as_float(q[g].z);
            mx = bmax2(mx, (q[g].y & 0xffffu) | (q[g].w << 16));
        }
        __syncwarp();
        t0 += __shfl_xor_sync(~0u, t0, 1); t1 += __shfl_xor_sync(~0u, t1, 1);
        mx = bmax2(mx, __shfl_xor_sync(~0u, mx, 1));
        const float g0 = rbf(t0 * (1.0f / ROWS)), g1 = rbf(t1 * (1.0f / ROWS));
        const float m0 = bf_lo(mx), m1 = bf_hi(mx);
        float a[4], c[4];
        a[0] = g0 * bf_lo(w1a.x) + g1 * bf_lo(w1b.x); c[0] = m0 * bf_lo(w1a.x) + m1 * bf_lo(w1b.x);
        a[1] = g0 * bf_hi(w1a.x) + g1 * bf_hi(w1b.x); c[1] = m0 * bf_hi(w1a.x) + m1 * bf_hi(w1b.x);
        a[2] = g0 * bf_lo(w1a.y) + g1 * bf_lo(w1b.y); c[2] = m0 * bf_lo(w1a.y) + m1 * bf_lo(w1b.y);
        a[3] = g0 * bf_hi(w1a.y) + g1 * bf_hi(w1b.y); c[3] = m0 * bf_hi(w1a.y) + m1 * bf_hi(w1b.y);
        const float e0 = rs_step<16>(a[0], c[0], lane), e1 = rs_step<16>(a[1], c[1], lane);
        const float e2 = rs_step<16>(a[2], c[2], lane), e3 = rs_step<16>(a[3], c[3], lane);
        const float f0 = rs_step<8>(e0, e2, lane), f1 = rs_step<8>(e1, e3, lane);
        float h = rs_step<4>(f0, f1, lane);
        h += __shfl_xor_sync(~0u, h, 2);
        if (!(lane & 2)) {
            const int unit = 4 * half + ((lane >> 3) & 1) * 2 + ((lane >> 2) & 1);
            misc[warp * 16 + unit * 2 + (lane >> 4)] = h;
        }
        __syncthreads();
        if (warp == 0) {
            float ha = 0.f, hm = 0.f;
#pragma unroll
            for (int w = 0; w < 12; w++) {
                const float2 v2 = *reinterpret_cast<const float2*>(misc + w * 16 + (lane & 7) * 2);
                ha += v2.x; hm += v2.y;
            }
            ha = rbf(ha); hm = rbf(hm);
            ha = ha * (ha > 0.f ? 1.f : 0.f);
            hm = hm * (hm > 0.f ? 1.f : 0.f);
            st_pkt8(&g_s.hid[lane >> 3][8 * b + (lane & 7)], f2bf(ha) | (f2bf(hm) << 16), tag32);
        }
        TS(3);
    }

    uint4 sc;
    {
        const void* p = &g_s.hid[b % NREP][(t >> 3) * 2];
        uint4 q;
        unsigned spins = 0;
        while (true) {
            q = ld_poll16(p);
            if (q.y == tag32 && q.w == tag32) break;
            if (++spins > SPIN_LIMIT) __trap();
        }
        __syncwarp();
        TS(4);
        const float ha0 = bf_lo(q.x), hm0 = bf_hi(q.x), ha1 = bf_lo(q.z), hm1 = bf_hi(q.z);
        float za[8], zm[8];
        const unsigned wa[4] = {w2a.x, w2a.y, w2a.z, w2a.w}, wb[4] = {w2b.x, w2b.y, w2b.z, w2b.w};
#pragma unroll
        for (int i = 0; i < 4; i++) {
            za[2 * i] = ha0 * bf_lo(wa[i]) + ha1 * bf_lo(wb[i]); za[2 * i + 1] = ha0 * bf_hi(wa[i]) + ha1 * bf_hi(wb[i]);
            zm[2 * i] = hm0 * bf_lo(wa[i]) + hm1 * bf_lo(wb[i]); zm[2 * i + 1] = hm0 * bf_hi(wa[i]) + hm1 * bf_hi(wb[i]);
        }
        float ya[4], ym[4];
#pragma unroll
        for (int i = 0; i < 4; i++) { ya[i] = rs_step<16>(za[i], za[4 + i], lane); ym[i] = rs_step<16>(zm[i], zm[4 + i], lane); }
        const float xa0 = rs_step<8>(ya[0], ya[2], lane), xa1 = rs_step<8>(ya[1], ya[3], lane);
        const float xm0 = rs_step<8>(ym[0], ym[2], lane), xm1 = rs_step<8>(ym[1], ym[3], lane);
        const int cp = (lane & 7) * 4 + (lane >> 4) * 2 + ((lane >> 3) & 1);
        sts16(sbase + SM_RED + (warp * 32 + cp) * 16,
              make_uint4(__float_as_uint(xa0), __float_as_uint(xm0), __float_as_uint(xa1), __float_as_uint(xm1)));
        __syncthreads();
        unsigned short* gates = reinterpret_cast<unsigned short*>(misc + 192);
        if (warp < 4) {
            const int cpp = warp * 8 + (lane & 7), sw = (lane >> 3) * 3;
            const uint4 e0 = lds16(sbase + SM_RED + ((sw + 0) * 32 + cpp) * 16);
            const uint4 e1 = lds16(sbase + SM_RED + ((sw + 1) * 32 + cpp) * 16);
            const uint4 e2 = lds16(sbase + SM_RED + ((sw + 2) * 32 + cpp) * 16);
            const float u0 = (__uint_as_float(e0.x) + __uint_as_float(e1.x)) + __uint_as_float(e2.x);
            const float u1 = (__uint_as_float(e0.y) + __uint_as_float(e1.y)) + __uint_as_float(e2.y);
            const float u2 = (__uint_as_float(e0.z) + __uint_as_float(e1.z)) + __uint_as_float(e2.z);
            const float u3 = (__uint_as_float(e0.w) + __uint_as_float(e1.w)) + __uint_as_float(e2.w);
            float va = rs_step<8>(u0, u2, lane), vm = rs_step<8>(u1, u3, lane);
            va += __shfl_xor_sync(~0u, va, 16); vm += __shfl_xor_sync(~0u, vm, 16);
            const float z = rbf(rbf(va) + rbf(vm));
            const unsigned sg = f2bf(1.0f / (1.0f + __expf(-z)));
            if (lane < 16) gates[cpp * 2 + (lane >> 3)] = (unsigned short)sg;
        }
        __syncthreads();
        sc = lds16(sbase + SM_MISC + 768 + (t & 7) * 16);
    }
    TS(5);
    if (b == 0 && t == 0) asm volatile("st.relaxed.gpu.global.u32 [%0], %1;" :: "l"(&g_s.epoch), "r"(epoch + 1u) : "memory");

    for (int u = warp * ng + grp; u < ovf_units; u += 12 * ng)
        stg16(out + ovf_base + (size_t)u * 4 * ROW_BYTES, scale4(ldg16(x + ovf_base + (size_t)u * 4 * ROW_BYTES), sc));
#pragma unroll
    for (int i = SMP; i < NP; i++)
        if (i < NP - 1 || last_ok) stg16(out + goff(i), scale4(d[i], sc));
    TS(6);
#pragma unroll 4
    for (int i = 0; i < SMP; i++) stg16(out + off0 + i * pstride, scale4(lds16(sm_t + i * PASS_BYTES), sc));
    TS(7);
}

__global__ void __launch_bounds__(NT, 1)
cbam_kernel(const char* __restrict__ x, const char* __restrict__ w1, const char* __restrict__ w2,
            char* __restrict__ out) {
    extern __shared__ __align__(128) char smem[];
    if (blockIdx.x < NL1) body<true>(x, w1, w2, out, smem);
    else body<false>(x, w1, w2, out, smem);
}

}

extern "C" void kernel_launch(void* const* d_in, const int* in_sizes, int n_in, void* d_out, int out_size) {
    using namespace cbam;
    static int grid = 0;
    if (grid == 0) {
        int dev = 0, sms = 0;
        cudaGetDevice(&dev);
        cudaDeviceGetAttribute(&sms, cudaDevAttrMultiProcessorCount, dev);
        cudaFuncSetAttribute(cbam_kernel, cudaFuncAttributeMaxDynamicSharedMemorySize, SM_TOTAL);
        int ng = sms / NS;
        if (ng > MAXNG) ng = MAXNG;
        grid = ng * NS;
    }
    const char* x = (const char*)d_in[0];
    const char* w1 = (const char*)d_in[1];
    const char* w2 = (const char*)d_in[2];
    char* out = (char*)d_out;
    void* args[] = {(void*)&x, (void*)&w1, (void*)&w2, (void*)&out};
    cudaLaunchCooperativeKernel((const void*)cbam_kernel, dim3(grid), dim3(NT), args, SM_TOTAL, cudaStreamPerThread);
}
```

```cpp
#include <cuda_runtime.h>
#include <cuda_bf16.h>
#include <stdint.h>

namespace cbam {

typedef unsigned long long u64;

constexpr int C = 384;
constexpr int HID = 96;
constexpr int NT = 384;
constexpr int ROWS = 65536;
constexpr int ROW_BYTES = C * 2;
constexpr int NS = 6;
constexpr int NG = 22;
constexpr int GRID = NS * NG;
constexpr int PROWS = 48;
constexpr int PASS_BYTES = NT * 16;
constexpr int SMP = 36;
constexpr int RGP = 28;
constexpr int RGL = 8;
constexpr int NPN = SMP + RGP;
constexpr int NPL = SMP + RGL;
constexpr int WIN = 10;
constexpr int NL1 = 12;
constexpr int L1G = NL1 / NS;
constexpr int NREP = 24;
constexpr unsigned SPIN_LIMIT = 1u << 22;
constexpr unsigned BLK = PROWS * ROW_BYTES;
static_assert((NG * NPL + (NG - L1G) * (NPN - NPL)) * PROWS >= ROWS, "on-chip capacity");
static_assert((NG * NPL + (NG - L1G) * (NPN - 1 - NPL)) * PROWS <= ROWS, "only the last pass may run past the end");

struct __align__(128) Scratch {
    uint4 part[NS][NG][32];
    u64 hid[NREP][NL1][2][4];
    unsigned epoch;
    __align__(16) float fsum[256][C];
    __align__(16) float fmax[256][C];
    __align__(16) unsigned short fgate[C];
};
__device__ Scratch g_s;

constexpr int SM_DATA = SMP * PASS_BYTES;
constexpr int SM_RED = SM_DATA;
constexpr int SM_L1 = SM_RED + 6144;
constexpr int SM_L2 = SM_L1 + 768;
constexpr int SM_HID = SM_L2 + 1536;
constexpr int SM_TOTAL = SM_HID + 384;

__device__ __forceinline__ void stg16(void* p, uint4 v) {
    asm volatile("st.global.v4.u32 [%0], {%1,%2,%3,%4};" :: "l"(p), "r"(v.x), "r"(v.y), "r"(v.z), "r"(v.w) : "memory");
}
__device__ __forceinline__ uint4 lds16(unsigned a) {
    uint4 v;
    asm volatile("ld.shared.v4.u32 {%0,%1,%2,%3}, [%4];" : "=r"(v.x), "=r"(v.y), "=r"(v.z), "=r"(v.w) : "r"(a) : "memory");
    return v;
}
__device__ __forceinline__ float2 lds8f(unsigned a) {
    float2 v;
    asm volatile("ld.shared.v2.f32 {%0,%1}, [%2];" : "=f"(v.x), "=f"(v.y) : "r"(a) : "memory");
    return v;
}
__device__ __forceinline__ void sts16(unsigned a, uint4 v) {
    asm volatile("st.shared.v4.u32 [%0], {%1,%2,%3,%4};" :: "r"(a), "r"(v.x), "r"(v.y), "r"(v.z), "r"(v.w) : "memory");
}
__device__ __forceinline__ void ld_pkt16_if(u64& a, u64& b, const void* p, unsigned pred) {
    asm volatile("{ .reg .pred p; setp.ne.u32 p, %3, 0; @p ld.relaxed.gpu.global.v2.b64 {%0,%1}, [%2]; }"
                 : "+l"(a), "+l"(b) : "l"(p), "r"(pred) : "memory");
}
__device__ __forceinline__ void st_pkt16(void* p, unsigned a, unsigned b, unsigned c, unsigned d) {
    const u64 r0 = (u64)a | ((u64)b << 32), r1 = (u64)c | ((u64)d << 32);
    asm volatile("st.relaxed.gpu.global.v2.b64 [%0], {%1,%2};" :: "l"(p), "l"(r0), "l"(r1) : "memory");
}
__device__ __forceinline__ void st_pkt8(void* p, unsigned lo, unsigned hi) {
    const u64 r = (u64)lo | ((u64)hi << 32);
    asm volatile("st.relaxed.gpu.global.b64 [%0], %1;" :: "l"(p), "l"(r) : "memory");
}
__device__ __forceinline__ unsigned bmax2(unsigned a, unsigned b) {
    unsigned r;
    asm("max.NaN.bf16x2 %0, %1, %2;" : "=r"(r) : "r"(a), "r"(b));
    return r;
}
__device__ __forceinline__ unsigned bmul2(unsigned a, unsigned b) {
    unsigned r;
    asm("mul.rn.bf16x2 %0, %1, %2;" : "=r"(r) : "r"(a), "r"(b));
    return r;
}
__device__ __forceinline__ float bf_lo(unsigned u) { return __uint_as_float(u << 16); }
__device__ __forceinline__ float bf_hi(unsigned u) { return __uint_as_float(u & 0xffff0000u); }
__device__ __forceinline__ float rbf(float f) { return __bfloat162float(__float2bfloat16_rn(f)); }
__device__ __forceinline__ unsigned lo32(u64 v) { return (unsigned)v; }
__device__ __forceinline__ unsigned hi32(u64 v) { return (unsigned)(v >> 32); }
__device__ __forceinline__ float asf(unsigned u) { return __uint_as_float(u); }

__device__ __forceinline__ void accum(const uint4& v, float (&s)[8], unsigned (&m)[4]) {
    s[0] += bf_lo(v.x); s[1] += bf_hi(v.x);
    s[2] += bf_lo(v.y); s[3] += bf_hi(v.y);
    s[4] += bf_lo(v.z); s[5] += bf_hi(v.z);
    s[6] += bf_lo(v.w); s[7] += bf_hi(v.w);
    m[0] = bmax2(m[0], v.x); m[1] = bmax2(m[1], v.y);
    m[2] = bmax2(m[2], v.z); m[3] = bmax2(m[3], v.w);
}
__device__ __forceinline__ uint4 scale4(const uint4& v, const uint4& sc) {
    return make_uint4(bmul2(v.x, sc.x), bmul2(v.y, sc.y), bmul2(v.z, sc.z), bmul2(v.w, sc.w));
}
template <int MASK>
__device__ __forceinline__ float rs_step(float lo, float hi, int lane) {
    const bool up = lane & MASK;
    const float keep = up ? hi : lo, send = up ? lo : hi;
    return keep + __shfl_xor_sync(~0u, send, MASK);
}
template <int MASK>
__device__ __forceinline__ unsigned rs_step_max(unsigned lo, unsigned hi, int lane) {
    const bool up = lane & MASK;
    const unsigned keep = up ? hi : lo, send = up ? lo : hi;
    return bmax2(keep, __shfl_xor_sync(~0u, send, MASK));
}
__device__ __forceinline__ unsigned pack_bf2(float lo, float hi) {
    unsigned r;
    asm("cvt.rn.bf16x2.f32 %0, %1, %2;" : "=r"(r) : "f"(hi), "f"(lo));
    return r;
}
__device__ __forceinline__ void mma16816(float (&c)[4], unsigned a0, unsigned a1, unsigned a2, unsigned a3,
                                         unsigned b0, unsigned b1) {
    asm volatile("mma.sync.aligned.m16n8k16.row.col.f32.bf16.bf16.f32 {%0,%1,%2,%3}, {%4,%5,%6,%7}, {%8,%9}, {%0,%1,%2,%3};"
                 : "+f"(c[0]), "+f"(c[1]), "+f"(c[2]), "+f"(c[3]) : "r"(a0), "r"(a1), "r"(a2), "r"(a3), "r"(b0), "r"(b1));
}
__device__ __forceinline__ unsigned ldg4(const void* p) {
    unsigned v;
    asm volatile("ld.global.nc.u32 %0, [%1];" : "=r"(v) : "l"(p) : "memory");
    return v;
}
__device__ __forceinline__ unsigned ldg2(const void* p) {
    unsigned short v;
    asm volatile("ld.global.nc.u16 %0, [%1];" : "=h"(v) : "l"(p) : "memory");
    return v;
}
__device__ __forceinline__ float sigmoidf(float z) {
    float e, r;
    asm("ex2.approx.ftz.f32 %0, %1;" : "=f"(e) : "f"(z * -1.4426950408889634f));
    asm("rcp.approx.ftz.f32 %0, %1;" : "=f"(r) : "f"(fmaf(e, 0x1p-32f, 0x1p-32f)));
    return r * 0x1p-32f;
}
__device__ __forceinline__ unsigned pin(unsigned v) { return __shfl_sync(~0u, v, threadIdx.x & 31); }
__device__ __forceinline__ unsigned prmt_now(unsigned a, unsigned b, unsigned sel) {
    unsigned r;
    asm volatile("prmt.b32 %0, %1, %2, %3;" : "=r"(r) : "r"(a), "r"(b), "r"(sel));
    return r;
}

__host__ __device__ constexpr unsigned pass_off(int i) {
    return i < NPL ? (unsigned)i * NG * BLK : (unsigned)(NPL * NG - L1G + (i - NPL) * (NG - L1G)) * BLK;
}
template <int V> struct IC { static constexpr int value = V; };
template <int B, int E, class F>
__device__ __forceinline__ void static_for(F&& f) {
    if constexpr (B < E) { f(IC<B>{}); static_for<B + 1, E>(f); }
}

template <bool L1>
__device__ __forceinline__ void body(const char* __restrict__ x, const char* __restrict__ w1,
                                     const char* __restrict__ w2, char* __restrict__ out, Scratch* gs, char* smem) {
    constexpr int NP = L1 ? NPL : NPN;
    constexpr int RG = NP - SMP;
    const int t = threadIdx.x, lane = t & 31, warp = t >> 5;
    const int b = blockIdx.x;
    const int slice = b % NS, grp = b / NS;

    u64 pol_first;
    asm volatile("createpolicy.fractional.L2::evict_first.b64 %0, 1.0;" : "=l"(pol_first));

    const unsigned off0 = (unsigned)(grp * PROWS + (t >> 3)) * ROW_BYTES + slice * 128 + (t & 7) * 16;
    const char* xp = x + off0;
    const bool last_ok = L1 || off0 + pass_off(NP - 1) < (unsigned)ROWS * ROW_BYTES;
    const unsigned sbase = (unsigned)__cvta_generic_to_shared(smem);
    const unsigned sm_t = sbase + t * 16;
    const unsigned sm_o = __shfl_sync(~0u, sm_t, lane);

    float s[8];
    unsigned m[4];
#pragma unroll
    for (int i = 0; i < 8; i++) s[i] = 0.f;
#pragma unroll
    for (int i = 0; i < 4; i++) m[i] = 0xff80ff80u;

    uint4 d[RG];
    unsigned epoch;
    const unsigned zero = gridDim.y - 1u;
    auto step = [&](auto nc) {
        constexpr int n = decltype(nc)::value;
        if constexpr (n < NP) {
            constexpr int i = n < RG ? SMP + n : n - RG;
            constexpr int slot = n < RG ? SMP - RG + n : n - RG;
            if constexpr (i < NP - 1) {
                asm volatile("cp.async.cg.shared.global.L2::cache_hint [%0], [%1], 16, %2;\n\tcp.async.commit_group;"
                             :: "r"(sm_o + slot * PASS_BYTES), "l"(xp + pass_off(i)), "l"(pol_first) : "memory");
            } else {
                asm volatile("{ .reg .pred p; setp.ne.u32 p, %3, 0;\n\t"
                             "@p cp.async.cg.shared.global.L2::cache_hint [%0], [%1], 16, %2;\n\tcp.async.commit_group; }"
                             :: "r"(sm_o + slot * PASS_BYTES), "l"(xp + pass_off(i)), "l"(pol_first), "r"((unsigned)last_ok) : "memory");
            }
        }
        if constexpr (n == WIN - 1)
            asm volatile("ld.relaxed.gpu.global.u32 %0, [%1];" : "=r"(epoch) : "l"(&gs->epoch) : "memory");
        if constexpr (L1 && n == WIN - 1) {
            const char* wp = (t < 48 ? w1 : w2 - 48 * 128) + (b * 48 + t) * 128;
            asm volatile("{ .reg .pred p; setp.ne.u32 p, %1, 0; @p prefetch.global.L2 [%0]; }" :: "l"(wp), "r"((unsigned)(t < 96)));
        }
        if constexpr (n >= WIN) {
            constexpr int c = n - WIN;
            constexpr int slot = c < RG ? SMP - RG + c : c - RG;
            if constexpr (n >= NP + WIN - 2) {
                const unsigned dep = (__float_as_uint(s[0]) | __float_as_uint(s[1]) | __float_as_uint(s[2])) &
                                     (__float_as_uint(s[3]) | __float_as_uint(s[4]) | __float_as_uint(s[5])) &
                                     (__float_as_uint(s[6]) | __float_as_uint(s[7]) | m[0]) & (m[1] | m[2] | m[3]) & zero;
                asm volatile("{ .reg .pred p; setp.eq.u32 p, %1, 0; @p cp.async.wait_group %0; }"
                             :: "n"(NP - 1 - c), "r"(dep) : "memory");
            } else {
                asm volatile("cp.async.wait_group %0;" :: "n"((n < NP ? n : NP - 1) - c) : "memory");
            }
            const uint4 v = lds16(sm_t + slot * PASS_BYTES);
            if constexpr (c < RG) d[c] = v;
            if (c != RG - 1 || last_ok) accum(v, s, m);
        }
    };
    static_for<0, RG + WIN>(step);
    {
        static_assert((SMP - WIN) % 2 == 0, "rolled by two");
        const char* gp = xp + (size_t)WIN * (NG * BLK);
        unsigned sa = sm_o;
#pragma unroll 1
        for (int it = 0; it < (SMP - WIN) / 2; it++) {
#pragma unroll
            for (int k = 0; k < 2; k++) {
                asm volatile("cp.async.cg.shared.global.L2::cache_hint [%0], [%1], 16, %2;\n\tcp.async.commit_group;\n\t"
                             "cp.async.wait_group %3;"
                             :: "r"(sa + (WIN + k) * PASS_BYTES), "l"(gp + (size_t)k * (NG * BLK)), "l"(pol_first), "n"(WIN) : "memory");
                accum(lds16(sa + k * PASS_BYTES), s, m);
            }
            gp += (size_t)2 * (NG * BLK);
            sa += 2 * PASS_BYTES;
        }
    }
    const unsigned red_w = pin(sbase + SM_RED + (warp * 32 + (lane & 7) * 4 + (lane >> 4) * 2 + ((lane >> 3) & 1)) * 16);
    const unsigned red_r = pin(sbase + SM_RED + ((lane >> 3) * 3 * 32 + (warp & 3) * 8 + (lane & 7)) * 16);
    const unsigned pub_o = pin(((slice * NG + grp) * 32 + (warp & 3) * 8 + (lane & 7)) * 16);
    static_for<NP, NP + WIN>(step);
    const unsigned tag32 = epoch + 1u;
    const unsigned tag16 = tag32 << 16;
    const int fg = lane >> 2, fq = lane & 3;

    {
        const float a0 = rs_step<16>(s[0], s[4], lane), a1 = rs_step<16>(s[1], s[5], lane);
        const float a2 = rs_step<16>(s[2], s[6], lane), a3 = rs_step<16>(s[3], s[7], lane);
        const unsigned k0 = rs_step_max<16>(m[0], m[2], lane), k1 = rs_step_max<16>(m[1], m[3], lane);
        const float c0 = rs_step<8>(a0, a2, lane), c1 = rs_step<8>(a1, a3, lane);
        const unsigned km = rs_step_max<8>(k0, k1, lane);
        sts16(red_w, make_uint4(__float_as_uint(c0), __float_as_uint(c1), km, 0u));
        __syncthreads();
        if (warp < 4) {
            const uint4 e0 = lds16(red_r), e1 = lds16(red_r + 512), e2 = lds16(red_r + 1024);
            float u0 = (asf(e0.x) + asf(e1.x)) + asf(e2.x), u1 = (asf(e0.y) + asf(e1.y)) + asf(e2.y);
            unsigned um = bmax2(bmax2(e0.z, e1.z), e2.z);
            u0 += __shfl_xor_sync(~0u, u0, 8); u1 += __shfl_xor_sync(~0u, u1, 8); um = bmax2(um, __shfl_xor_sync(~0u, um, 8));
            u0 += __shfl_xor_sync(~0u, u0, 16); u1 += __shfl_xor_sync(~0u, u1, 16); um = bmax2(um, __shfl_xor_sync(~0u, um, 16));
            if (lane < 8)
                st_pkt16(reinterpret_cast<char*>(gs->part) + pub_o, __float_as_uint(u0), (um & 0xffffu) | tag16,
                         __float_as_uint(u1), (um >> 16) | tag16);
        }
    }

    if constexpr (L1) {
        unsigned wr1[8];
        {
            const char* wp = w1 + ((size_t)(warp * 32 + fq * 8) * HID + 8 * b + fg) * 2;
#pragma unroll
            for (int i = 0; i < 8; i++) wr1[i] = ldg2(wp + i * HID * 2);
        }
        constexpr int HG = NG / 2;
        const int half = lane >> 4;
        const uint4* src = &gs->part[warp >> 1][half * HG][(warp & 1) * 16 + (lane & 15)];
        const unsigned wb0 = prmt_now(wr1[0], wr1[1], 0x5410), wb1 = prmt_now(wr1[2], wr1[3], 0x5410);
        const unsigned wb2 = prmt_now(wr1[4], wr1[5], 0x5410), wb3 = prmt_now(wr1[6], wr1[7], 0x5410);
        const unsigned l1_w = pin(sbase + SM_L1 + (warp * 8 + (lane & 7)) * 8);
        const unsigned l1_r = pin(sbase + SM_L1 + ((lane >> 3) * 24 + (lane & 7)) * 8);
        const unsigned hid_o = pin((((warp * 4 + (lane >> 3)) * NL1 + b) * 8 + (lane & 7)) * 8);
        const unsigned af_src = pin(4 * fq + (fg & 1) * 16);
        u64 qa[HG], qb[HG];
#pragma unroll
        for (int g = 0; g < HG; g++) { qa[g] = 0; qb[g] = 0; }
        unsigned pending = (1u << HG) - 1u, spins = 0;
        do {
#pragma unroll
            for (int g = 0; g < HG; g++) ld_pkt16_if(qa[g], qb[g], src + g * 32, pending & (1u << g));
            unsigned ok = 0;
#pragma unroll
            for (int g = 0; g < HG; g++) ok |= (((hi32(qa[g]) ^ tag16) | (hi32(qb[g]) ^ tag16)) < 0x10000u) ? (1u << g) : 0u;
            pending &= ~__reduce_and_sync(~0u, ok);
            if (++spins > SPIN_LIMIT) __trap();
        } while (pending);
        float f0[HG], f1[HG];
        unsigned mq[HG];
#pragma unroll
        for (int g = 0; g < HG; g++) { f0[g] = asf(lo32(qa[g])); f1[g] = asf(lo32(qb[g])); mq[g] = __byte_perm(hi32(qa[g]), hi32(qb[g]), 0x5410); }
#pragma unroll
        for (int st = 1; st < HG; st <<= 1)
#pragma unroll
            for (int g = 0; g + st < HG; g += 2 * st) { f0[g] += f0[g + st]; f1[g] += f1[g + st]; mq[g] = bmax2(mq[g], mq[g + st]); }
        const float o0 = __shfl_xor_sync(~0u, f0[0], 16), o1 = __shfl_xor_sync(~0u, f1[0], 16);
        const unsigned om = __shfl_xor_sync(~0u, mq[0], 16);
        const unsigned mine = half ? bmax2(mq[0], om) : pack_bf2((f0[0] + o0) * (1.0f / ROWS), (f1[0] + o1) * (1.0f / ROWS));
        unsigned af[4];
#pragma unroll
        for (int i = 0; i < 4; i++) af[i] = __shfl_sync(~0u, mine, af_src + i);
        float c[4] = {0.f, 0.f, 0.f, 0.f}, c2[4] = {0.f, 0.f, 0.f, 0.f};
        mma16816(c, af[0], 0u, af[1], 0u, wb0, wb1);
        mma16816(c2, af[2], 0u, af[3], 0u, wb2, wb3);
        if (lane < 8)
            asm volatile("st.shared.v2.f32 [%0], {%1,%2};" :: "r"(l1_w), "f"(c[0] + c2[0]), "f"(c[1] + c2[1]) : "memory");
        if (warp >= NREP / 4) {
            asm volatile("bar.arrive 1, 384;" ::: "memory");
        } else {
            asm volatile("bar.sync 1, 384;" ::: "memory");
            const float2 v0 = lds8f(l1_r), v1 = lds8f(l1_r + 64), v2 = lds8f(l1_r + 128);
            float h0 = (v0.x + v1.x) + v2.x, h1 = (v0.y + v1.y) + v2.y;
            h0 += __shfl_xor_sync(~0u, h0, 8); h1 += __shfl_xor_sync(~0u, h1, 8);
            h0 += __shfl_xor_sync(~0u, h0, 16); h1 += __shfl_xor_sync(~0u, h1, 16);
            const unsigned hp = pack_bf2(h0, h1);
            unsigned mask;
            asm("set.gt.bf16x2.bf16x2 %0, %1, %2;" : "=r"(mask) : "r"(hp), "r"(0u));
            st_pkt8(reinterpret_cast<char*>(gs->hid) + hid_o, bmul2(hp, mask), tag32);
        }
    }

    unsigned wr2[8];
    {
        const char* wp = w2 + (size_t)((warp >> 2) * 32 + fq * 8) * ROW_BYTES + slice * 128 + (warp & 3) * 32 + fg * 4;
#pragma unroll
        for (int i = 0; i < 8; i++) wr2[i] = ldg4(wp + i * ROW_BYTES);
    }

    uint4 sc;
    {
        const u64* hp = &gs->hid[b % NREP][(warp >> 2) * 4][0][lane];
        const unsigned st_w = pin(sbase + SM_HID + ((warp >> 2) * 32 + lane) * 4);
        const unsigned st_r = pin(sbase + SM_HID + ((warp >> 2) * 32 + fq * 8 + (fg & 1) * 4) * 4);
        const unsigned l2_w = pin(sbase + SM_L2 + ((warp >> 2) * 32 + (warp & 3) * 8 + fg) * 16);
        const unsigned l2_r = pin(sbase + SM_L2 + lane * 16);
        const unsigned sc_src = pin((lane & 7) * 4);
        unsigned wa[8];
#pragma unroll
        for (int i = 0; i < 4; i++) {
            wa[2 * i] = prmt_now(wr2[2 * i], wr2[2 * i + 1], 0x5410);
            wa[2 * i + 1] = prmt_now(wr2[2 * i], wr2[2 * i + 1], 0x7632);
        }
        if ((warp & 3) == 3) {
            u64 q;
            unsigned spins = 0;
            do {
                asm volatile("ld.relaxed.gpu.global.b64 %0, [%1];" : "=l"(q) : "l"(hp) : "memory");
                if (++spins > SPIN_LIMIT) __trap();
            } while (__any_sync(~0u, hi32(q) != tag32));
            asm volatile("st.shared.u32 [%0], %1;" :: "r"(st_w), "r"(lo32(q)) : "memory");
        }
        asm volatile("bar.sync %0, 128;" :: "r"(2 + (warp >> 2)) : "memory");
        const uint4 bf = lds16(st_r);
        float c[4] = {0.f, 0.f, 0.f, 0.f}, c2[4] = {0.f, 0.f, 0.f, 0.f};
        mma16816(c, wa[0], wa[1], wa[2], wa[3], bf.x, bf.y);
        mma16816(c2, wa[4], wa[5], wa[6], wa[7], bf.z, bf.w);
        if (fq == 0)
            sts16(l2_w, make_uint4(__float_as_uint(c[0] + c2[0]), __float_as_uint(c[1] + c2[1]), __float_as_uint(c[2] + c2[2]),
                                   __float_as_uint(c[3] + c2[3])));
        __syncthreads();
        const uint4 e0 = lds16(l2_r), e1 = lds16(l2_r + 512), e2 = lds16(l2_r + 1024);
        const unsigned pa = pack_bf2((asf(e0.x) + asf(e1.x)) + asf(e2.x), (asf(e0.z) + asf(e1.z)) + asf(e2.z));
        const unsigned pm = pack_bf2((asf(e0.y) + asf(e1.y)) + asf(e2.y), (asf(e0.w) + asf(e1.w)) + asf(e2.w));
        const unsigned pz = pack_bf2(bf_lo(pa) + bf_lo(pm), bf_hi(pa) + bf_hi(pm));
        const unsigned g2 = pack_bf2(sigmoidf(bf_lo(pz)), sigmoidf(bf_hi(pz)));
        sc.x = __shfl_sync(~0u, g2, sc_src); sc.y = __shfl_sync(~0u, g2, sc_src + 1);
        sc.z = __shfl_sync(~0u, g2, sc_src + 2); sc.w = __shfl_sync(~0u, g2, sc_src + 3);
    }
    if (L1 && b == 0 && t == 0)
        asm volatile("st.relaxed.gpu.global.u32 [%0], %1;" :: "l"(&gs->epoch), "r"(epoch + 1u) : "memory");

    char* op = out + off0;
#pragma unroll
    for (int i = 0; i < RG; i++)
        if (i < RG - 1 || last_ok) stg16(op + pass_off(SMP + i), scale4(d[i], sc));
#pragma unroll 4
    for (int i = 0; i < SMP; i++) stg16(op + (size_t)i * (NG * BLK), scale4(lds16(sm_t + i * PASS_BYTES), sc));
}

__global__ void __launch_bounds__(NT, 1)
cbam_kernel(const char* __restrict__ x, const char* __restrict__ w1, const char* __restrict__ w2,
            char* __restrict__ out, Scratch* gs) {
    extern __shared__ __align__(128) char smem[];
    if (blockIdx.x < NL1) body<true>(x, w1, w2, out, gs, smem);
    else body<false>(x, w1, w2, out, gs, smem);
}

__global__ void fb_reduce(const __nv_bfloat16* __restrict__ x) {
    const int c = threadIdx.x;
    float s = 0.f, m = -INFINITY;
    bool nan = false;
    for (int r = blockIdx.x * 256; r < blockIdx.x * 256 + 256; r++) {
        const float v = __bfloat162float(x[(size_t)r * C + c]);
        s += v; m = fmaxf(m, v); nan |= (v != v);
    }
    g_s.fsum[blockIdx.x][c] = s;
    g_s.fmax[blockIdx.x][c] = nan ? __int_as_float(0x7fc00000) : m;
}
__global__ void fb_mlp(const __nv_bfloat16* __restrict__ w1, const __nv_bfloat16* __restrict__ w2) {
    __shared__ float gap[C], gmp[C], ha[HID], hm[HID];
    const int c = threadIdx.x;
    float s = 0.f, m = -INFINITY;
    bool nan = false;
    for (int i = 0; i < 256; i++) { s += g_s.fsum[i][c]; const float v = g_s.fmax[i][c]; m = fmaxf(m, v); nan |= (v != v); }
    gap[c] = rbf(s * (1.0f / ROWS)); gmp[c] = nan ? __int_as_float(0x7fc00000) : m;
    __syncthreads();
    if (c < HID) {
        float a = 0.f, q = 0.f;
        for (int k = 0; k < C; k++) { const float w = __bfloat162float(w1[k * HID + c]); a += gap[k] * w; q += gmp[k] * w; }
        a = rbf(a); q = rbf(q);
        ha[c] = a * (a > 0.f ? 1.f : 0.f); hm[c] = q * (q > 0.f ? 1.f : 0.f);
    }
    __syncthreads();
    float a = 0.f, q = 0.f;
    for (int k = 0; k < HID; k++) { const float w = __bfloat162float(w2[k * C + c]); a += ha[k] * w; q += hm[k] * w; }
    g_s.fgate[c] = __bfloat16_as_ushort(__float2bfloat16_rn(sigmoidf(rbf(rbf(a) + rbf(q)))));
}
__global__ void fb_scale(const uint4* __restrict__ x, uint4* __restrict__ out) {
    const size_t i = (size_t)blockIdx.x * blockDim.x + threadIdx.x;
    const uint4 sc = *reinterpret_cast<const uint4*>(&g_s.fgate[(i % 48) * 8]);
    out[i] = scale4(x[i], sc);
}

}

extern "C" void kernel_launch(void* const* d_in, const int* in_sizes, int n_in, void* d_out, int out_size) {
    using namespace cbam;
    static int mode = -1;
    static Scratch* gs = nullptr;
    if (mode < 0) {
        int dev = 0, sms = 0, coop = 0, occ = 0;
        cudaGetDevice(&dev);
        cudaDeviceGetAttribute(&sms, cudaDevAttrMultiProcessorCount, dev);
        cudaDeviceGetAttribute(&coop, cudaDevAttrCooperativeLaunch, dev);
        mode = 0;
        if (coop && cudaFuncSetAttribute(cbam_kernel, cudaFuncAttributeMaxDynamicSharedMemorySize, SM_TOTAL) == cudaSuccess &&
            cudaOccupancyMaxActiveBlocksPerMultiprocessor(&occ, cbam_kernel, NT, SM_TOTAL) == cudaSuccess &&
            occ * sms >= GRID && cudaGetSymbolAddress((void**)&gs, g_s) == cudaSuccess)
            mode = 1;
        (void)cudaGetLastError();
    }
    const char* x = (const char*)d_in[0];
    const char* w1 = (const char*)d_in[1];
    const char* w2 = (const char*)d_in[2];
    char* out = (char*)d_out;
    if (mode == 1) {
        void* args[] = {(void*)&x, (void*)&w1, (void*)&w2, (void*)&out, (void*)&gs};
        cudaLaunchCooperativeKernel((const void*)cbam_kernel, dim3(GRID), dim3(NT), args, SM_TOTAL, cudaStreamPerThread);
    } else {
        fb_reduce<<<256, C, 0, cudaStreamPerThread>>>((const __nv_bfloat16*)x);
        fb_mlp<<<1, C, 0, cudaStreamPerThread>>>((const __nv_bfloat16*)w1, (const __nv_bfloat16*)w2);
        fb_scale<<<ROWS * 48 / 256, 256, 0, cudaStreamPerThread>>>((const uint4*)x, (uint4*)out);
    }
}
```
